```python
import torch

def _softmax(x, axis=-1):
    return torch.softmax(x, dim=axis)
def _gelu(x):
    return torch.nn.functional.gelu(x, approximate="tanh")
def _silu(x):
    return torch.nn.functional.silu(x)
def _sigmoid(x):
    return torch.sigmoid(x)
def _layernorm(x, axis=-1, eps=1e-5):
    m = x.mean(dim=axis, keepdim=True)
    v = x.var(dim=axis, keepdim=True, unbiased=False)
    return (x - m) / torch.sqrt(v + eps)
def _scatter_add(tgt, idx, src, axis=0):
    return tgt.clone().index_add_(axis, idx, src)
def _segment_sum(src, seg, n):
    out = torch.zeros((n,) + src.shape[1:], dtype=src.dtype)
    return out.index_add_(0, seg, src)
def _pad(x, pw):
    flat = tuple(v for pair in reversed(pw) for v in pair)
    return torch.nn.functional.pad(x, flat)

kernel_name = 'concat_heads__gqa_block_cached__mha_block_cached__decode'

def setup_inputs():

    _w = (lambda a: (lambda t: t.to(torch.bfloat16) if t.is_floating_point() else t)(torch.as_tensor(a)))
    def _A_setup():
        B, Sq, D = 1, 1, 448
        Hq, Hkv, Sk, Dh = 16, 8, 32768, 256
        assert Hq % Hkv == 0, (Hq, Hkv)
        return {
            "x": _w((lambda *s: torch.randn(*s, dtype=torch.bfloat16) * 0.8)(B, Sq, D)),
            "k_cache": _w((lambda *s: torch.randn(*s, dtype=torch.bfloat16) * 1.6)(B, Hkv, Sk, Dh)),
            "v_cache": _w((lambda *s: torch.randn(*s, dtype=torch.bfloat16) * 0.2)(B, Hkv, Sk, Dh)),
            "wq": _w((lambda *s: torch.randn(*s, dtype=torch.bfloat16) * 1.6)(D, Hq * Dh) * (D ** -0.5)),
            "wo": _w((lambda *s: torch.randn(*s, dtype=torch.bfloat16) * 0.2)(Hq * Dh, D) * ((Hq * Dh) ** -0.5)),
        }
    _A_in = _A_setup()

    def _B_setup():
        B, Sq, D = 1, 1, 448
        H, Sk, Dh = 16, 32768, 256
        return {
            "x": _w((lambda *s: torch.randn(*s, dtype=torch.bfloat16) * 0.8)(B, Sq, D)),
            "k_cache": _w((lambda *s: torch.randn(*s, dtype=torch.bfloat16) * 1.6)(B, H, Sk, Dh)),
            "v_cache": _w((lambda *s: torch.randn(*s, dtype=torch.bfloat16) * 0.2)(B, H, Sk, Dh)),
            "wq": _w((lambda *s: torch.randn(*s, dtype=torch.bfloat16) * 1.6)(D, H * Dh) * (D ** -0.5)),
            "wo": _w((lambda *s: torch.randn(*s, dtype=torch.bfloat16) * 0.2)(H * Dh, D) * ((H * Dh) ** -0.5)),
        }
    _B_in = _B_setup()

    return {
        "A_x": _A_in["x"],
        "A_k_cache": _A_in["k_cache"],
        "A_v_cache": _A_in["v_cache"],
        "A_wq": _A_in["wq"],
        "A_wo": _A_in["wo"],
        "B_x": _B_in["x"],
        "B_k_cache": _B_in["k_cache"],
        "B_v_cache": _B_in["v_cache"],
        "B_wq": _B_in["wq"],
        "B_wo": _B_in["wo"],
    }

def reference(A_x, A_k_cache, A_v_cache, A_wq, A_wo, B_x, B_k_cache, B_v_cache, B_wq, B_wo):
    def _A_ref(x, k_cache, v_cache, wq, wo):
        B, Sq, D = x.shape
        Hq, Dh = 16, 256
        Hkv = k_cache.shape[1]
        rep = Hq // Hkv
        q = (lambda x, *d: x.permute(*d))((x @ wq).reshape(B, Sq, Hq, Dh), 0, 2, 1, 3)
        k = (lambda x, n, axis: torch.repeat_interleave(x, n, dim=axis))(k_cache, rep, axis=1)
        v = (lambda x, n, axis: torch.repeat_interleave(x, n, dim=axis))(v_cache, rep, axis=1)
        scores = torch.einsum("bhqd,bhkd->bhqk", q, k) * (Dh ** -0.5)
        p = _softmax(scores, axis=-1)
        o = torch.einsum("bhqk,bhkd->bhqd", p, v)
        return (lambda x, *d: x.permute(*d))(o, 0, 2, 1, 3).reshape(B, Sq, Hq * Dh) @ wo

    def _B_ref(x, k_cache, v_cache, wq, wo):
        B, Sq, D = x.shape
        H, Dh = 16, 256
        q = (lambda x, *d: x.permute(*d))((x @ wq).reshape(B, Sq, H, Dh), 0, 2, 1, 3)
        scores = torch.einsum("bhqd,bhkd->bhqk", q, k_cache) * (Dh ** -0.5)
        p = _softmax(scores, axis=-1)
        o = torch.einsum("bhqk,bhkd->bhqd", p, v_cache)
        return (lambda x, *d: x.permute(*d))(o, 0, 2, 1, 3).reshape(B, Sq, H * Dh) @ wo

    a = _A_ref(A_x, A_k_cache, A_v_cache, A_wq, A_wo)
    b = _B_ref(B_x, B_k_cache, B_v_cache, B_wq, B_wo)
    return torch.concatenate([a, b], axis=-1)
```

```cpp
#include <cuda_runtime.h>
#include <cuda_bf16.h>
#include <stdint.h>

namespace {

constexpr int D_MODEL   = 448;
constexpr int DH        = 256;
constexpr int SK        = 32768;
constexpr int NHEADS    = 16;
constexpr int NSTREAM   = 24;
constexpr int BLK_ROWS  = 32;
constexpr int BLK_BYTES = BLK_ROWS * DH * 2;
constexpr int NBLK      = SK / BLK_ROWS;
constexpr int NSLOTS    = 10;
constexpr int NCW       = 8;
constexpr int NCT       = NCW * 32;
constexpr int NTHREADS  = NCT + 32;
#define P_TEAMS 2
constexpr int PT        = P_TEAMS;
constexpr int SPT       = NSTREAM / PT;
constexpr int MAX_G     = 132;
constexpr int MAX_TS    = MAX_G / PT;
constexpr int PART_STRIDE = 260;
constexpr int NGEMV     = 128;

constexpr int SM_RING   = 0;
constexpr int SM_ST_O   = SM_RING + NSLOTS * BLK_BYTES;
constexpr int SM_ST_ML  = SM_ST_O + NCW * 2 * 256 * 4;
constexpr int SM_Q      = SM_ST_ML + NCW * 2 * 2 * 4;
constexpr int SM_RED    = SM_Q + 32 * 256 * 2;
constexpr int SM_OS     = SM_RED + 4 * 448 * 4;
constexpr int SM_BARS   = SM_OS + 64 * 4;
constexpr int SM_TOTAL  = SM_BARS + 2 * NSLOTS * 8;

constexpr float SCALE_LOG2E = 0.0625f * 1.4426950408889634f;

__device__ float    g_q[2][NHEADS * DH];
__device__ float    g_part[NSTREAM][MAX_TS][2][PART_STRIDE];
__device__ float    g_outp[2][64][D_MODEL];
__device__ unsigned g_bar_q;
__device__ unsigned g_bar_part;
__device__ unsigned g_bar_out[2];

__device__ __forceinline__ uint32_t smem_u32(const void* p) { return (uint32_t)__cvta_generic_to_shared(p); }
__device__ __forceinline__ void mbar_init(uint32_t bar, uint32_t count) {
    asm volatile("mbarrier.init.shared::cta.b64 [%0], %1;" :: "r"(bar), "r"(count) : "memory");
}
__device__ __forceinline__ void mbar_expect_tx(uint32_t bar, uint32_t bytes) {
    asm volatile("mbarrier.arrive.expect_tx.shared::cta.b64 _, [%0], %1;" :: "r"(bar), "r"(bytes) : "memory");
}
__device__ __forceinline__ void mbar_arrive(uint32_t bar) {
    asm volatile("mbarrier.arrive.shared::cta.b64 _, [%0];" :: "r"(bar) : "memory");
}
#define HANG(site, info) __trap()
__device__ __forceinline__ void mbar_wait(uint32_t bar, uint32_t parity, unsigned site = 0, unsigned info = 0) {
    uint32_t done;
    uint32_t spins = 0;
    do {
        asm volatile("{ .reg .pred p; mbarrier.try_wait.parity.shared::cta.b64 p, [%1], %2; selp.u32 %0, 1, 0, p; }"
                     : "=r"(done) : "r"(bar), "r"(parity) : "memory");
        if (++spins > (1u << 22)) { HANG(site, info); break; }
    } while (!done);
}
__device__ __forceinline__ void bulk_g2s(uint32_t dst, const void* src, uint32_t bytes, uint32_t bar, uint64_t pol) {
    asm volatile("cp.async.bulk.shared::cluster.global.mbarrier::complete_tx::bytes.L2::cache_hint [%0], [%1], %2, [%3], %4;"
                 :: "r"(dst), "l"(src), "r"(bytes), "r"(bar), "l"(pol) : "memory");
}
__device__ __forceinline__ uint4 lds128(uint32_t addr) {
    uint4 v;
    asm volatile("ld.shared.v4.u32 {%0,%1,%2,%3}, [%4];" : "=r"(v.x), "=r"(v.y), "=r"(v.z), "=r"(v.w) : "r"(addr));
    return v;
}
__device__ __forceinline__ void bar_consumers() { asm volatile("bar.sync 1, %0;" :: "n"(NCT) : "memory"); }
__device__ __forceinline__ unsigned ld_acquire(const unsigned* p) {
    unsigned v;
    asm volatile("ld.acquire.gpu.global.u32 %0, [%1];" : "=r"(v) : "l"(p) : "memory");
    return v;
}
__device__ __forceinline__ void spin_until(const unsigned* p, unsigned target) {
    unsigned spins = 0;
    while (ld_acquire(p) < target) {
        if (++spins > (1u << 22)) { HANG(99, target); break; }
    }
}
__device__ __forceinline__ float bf_lo(uint32_t u) { return __uint_as_float(u << 16); }
__device__ __forceinline__ float bf_hi(uint32_t u) { return __uint_as_float(u & 0xffff0000u); }
__device__ __forceinline__ void unpack8(const uint4& v, float (&f)[8]) {
    f[0] = bf_lo(v.x); f[1] = bf_hi(v.x); f[2] = bf_lo(v.y); f[3] = bf_hi(v.y);
    f[4] = bf_lo(v.z); f[5] = bf_hi(v.z); f[6] = bf_lo(v.w); f[7] = bf_hi(v.w);
}
__device__ __forceinline__ float bf16_round(float x) { return __bfloat162float(__float2bfloat16_rn(x)); }

__device__ __forceinline__ float transpose_reduce32(float (&v)[32], int lane) {
#pragma unroll
    for (int i = 0; i < 16; i++) {
        bool hi = lane & 16;
        float send = hi ? v[i] : v[i + 16];
        float keep = hi ? v[i + 16] : v[i];
        v[i] = keep + __shfl_xor_sync(0xffffffffu, send, 16);
    }
#pragma unroll
    for (int i = 0; i < 8; i++) {
        bool hi = lane & 8;
        float send = hi ? v[i] : v[i + 8];
        float keep = hi ? v[i + 8] : v[i];
        v[i] = keep + __shfl_xor_sync(0xffffffffu, send, 8);
    }
#pragma unroll
    for (int i = 0; i < 4; i++) {
        bool hi = lane & 4;
        float send = hi ? v[i] : v[i + 4];
        float keep = hi ? v[i + 4] : v[i];
        v[i] = keep + __shfl_xor_sync(0xffffffffu, send, 4);
    }
#pragma unroll
    for (int i = 0; i < 2; i++) {
        bool hi = lane & 2;
        float send = hi ? v[i] : v[i + 2];
        float keep = hi ? v[i + 2] : v[i];
        v[i] = keep + __shfl_xor_sync(0xffffffffu, send, 2);
    }
    {
        bool hi = lane & 1;
        float send = hi ? v[0] : v[1];
        float keep = hi ? v[1] : v[0];
        v[0] = keep + __shfl_xor_sync(0xffffffffu, send, 1);
    }
    return v[0];
}
__device__ __forceinline__ float warp_max(float v) {
#pragma unroll
    for (int o = 16; o > 0; o >>= 1) v = fmaxf(v, __shfl_xor_sync(0xffffffffu, v, o));
    return v;
}
__device__ __forceinline__ float warp_sum(float v) {
#pragma unroll
    for (int o = 16; o > 0; o >>= 1) v += __shfl_xor_sync(0xffffffffu, v, o);
    return v;
}

__device__ __forceinline__ int stream_j0(int u, int rank, int ts) {
    int off = (u * (NBLK % ts)) % ts;
    int j0 = rank + off;
    return j0 >= ts ? j0 - ts : j0;
}
__device__ __forceinline__ int stream_nblk(int j0, int ts) { return (NBLK - j0 + ts - 1) / ts; }

template <int NH>
__device__ __forceinline__ void consume_stream(unsigned char* smem, uint32_t smem_base, int warp, int lane,
                                               int seq0, int nblk, int qhead0, int stream, int rank) {
    const uint32_t bar_full  = smem_base + SM_BARS;
    const uint32_t bar_empty = bar_full + NSLOTS * 8;

    float q[NH][8];
#pragma unroll
    for (int h = 0; h < NH; h++) {
        uint4 qq = lds128(smem_base + SM_Q + (qhead0 + h) * (DH * 2) + lane * 16);
        unpack8(qq, q[h]);
    }
    float o[NH][8];
    float m_run[NH], l_lane[NH];
#pragma unroll
    for (int h = 0; h < NH; h++) {
        m_run[h] = -INFINITY; l_lane[h] = 0.f;
#pragma unroll
        for (int j = 0; j < 8; j++) o[h][j] = 0.f;
    }

    for (int k = 0; k < nblk; k++) {
        const int seq = seq0 + k;
        if ((seq & (NCW - 1)) != warp) {
            const int pos = 2 * seq;
            const int slot = pos % NSLOTS;
            const uint32_t ph = (pos / NSLOTS) & 1;
            mbar_wait(bar_full + slot * 8, ph, 5, pos);
            const int posv = pos + 1;
            const int slotv = posv % NSLOTS;
            const uint32_t phv = (posv / NSLOTS) & 1;
            mbar_wait(bar_full + slotv * 8, phv, 6, posv);
            continue;
        }
        {
            const int pos = 2 * seq;
            const int slot = pos % NSLOTS;
            const uint32_t ph = (pos / NSLOTS) & 1;
            mbar_wait(bar_full + slot * 8, ph, 1, pos);
            const uint32_t kb = smem_base + SM_RING + slot * BLK_BYTES + lane * 16;
            float acc[NH][32];
#pragma unroll
            for (int r = 0; r < 32; r++) {
                uint4 kk = lds128(kb + r * (DH * 2));
                float kf[8];
                unpack8(kk, kf);
#pragma unroll
                for (int h = 0; h < NH; h++) {
                    float a = q[h][0] * kf[0];
#pragma unroll
                    for (int j = 1; j < 8; j++) a = fmaf(q[h][j], kf[j], a);
                    acc[h][r] = a;
                }
            }
            __syncwarp();
            if (lane == 0) mbar_arrive(bar_empty + slot * 8);

            float p[NH];
#pragma unroll
            for (int h = 0; h < NH; h++) {
                float s = transpose_reduce32(acc[h], lane);
                float t = bf16_round(s) * SCALE_LOG2E;
                float bm = warp_max(t);
                float m_new = fmaxf(m_run[h], bm);
                float corr = exp2f(m_run[h] - m_new);
                p[h] = exp2f(t - m_new);
                l_lane[h] = l_lane[h] * corr + p[h];
                m_run[h] = m_new;
#pragma unroll
                for (int j = 0; j < 8; j++) o[h][j] *= corr;
            }
            const int posv = pos + 1;
            const int slotv = posv % NSLOTS;
            const uint32_t phv = (posv / NSLOTS) & 1;
            mbar_wait(bar_full + slotv * 8, phv, 2, posv);
            const uint32_t vb = smem_base + SM_RING + slotv * BLK_BYTES + lane * 16;
#pragma unroll
            for (int r = 0; r < 32; r++) {
                uint4 vv = lds128(vb + r * (DH * 2));
                float vf[8];
                unpack8(vv, vf);
#pragma unroll
                for (int h = 0; h < NH; h++) {
                    float pr = __shfl_sync(0xffffffffu, p[h], r);
#pragma unroll
                    for (int j = 0; j < 8; j++) o[h][j] = fmaf(pr, vf[j], o[h][j]);
                }
            }
            __syncwarp();
            if (lane == 0) mbar_arrive(bar_empty + slotv * 8);
        }
    }

    float* st_o  = reinterpret_cast<float*>(smem + SM_ST_O);
    float* st_ml = reinterpret_cast<float*>(smem + SM_ST_ML);
#pragma unroll
    for (int h = 0; h < NH; h++) {
        float lw = warp_sum(l_lane[h]);
        float4* dst = reinterpret_cast<float4*>(st_o + (warp * 2 + h) * DH + lane * 8);
        dst[0] = make_float4(o[h][0], o[h][1], o[h][2], o[h][3]);
        dst[1] = make_float4(o[h][4], o[h][5], o[h][6], o[h][7]);
        if (lane == 0) { st_ml[(warp * 2 + h) * 2] = m_run[h]; st_ml[(warp * 2 + h) * 2 + 1] = lw; }
    }
    bar_consumers();
    {
        const int t = warp * 32 + lane;
#pragma unroll
        for (int h = 0; h < NH; h++) {
            float M = -INFINITY;
#pragma unroll
            for (int w = 0; w < NCW; w++) M = fmaxf(M, st_ml[(w * 2 + h) * 2]);
            float acc = 0.f, L = 0.f;
#pragma unroll
            for (int w = 0; w < NCW; w++) {
                float sc = exp2f(st_ml[(w * 2 + h) * 2] - M);
                acc = fmaf(st_o[(w * 2 + h) * DH + t], sc, acc);
                L = fmaf(st_ml[(w * 2 + h) * 2 + 1], sc, L);
            }
            float* dst = &g_part[stream][rank][h][0];
            dst[t] = acc;
            if (t == 0) { dst[256] = M; dst[257] = L; }
        }
    }
    bar_consumers();
}

__global__ void __launch_bounds__(NTHREADS, 1)
fused_decode_kernel(const __nv_bfloat16* __restrict__ Ax, const __nv_bfloat16* __restrict__ Ak,
                    const __nv_bfloat16* __restrict__ Av, const __nv_bfloat16* __restrict__ Awq,
                    const __nv_bfloat16* __restrict__ Awo, const __nv_bfloat16* __restrict__ Bx,
                    const __nv_bfloat16* __restrict__ Bk, const __nv_bfloat16* __restrict__ Bv,
                    const __nv_bfloat16* __restrict__ Bwq, const __nv_bfloat16* __restrict__ Bwo,
                    __nv_bfloat16* __restrict__ out) {
    extern __shared__ __align__(128) unsigned char smem[];
    const uint32_t smem_base = smem_u32(smem);
    const int tid = threadIdx.x, warp = tid >> 5, lane = tid & 31;
    const int G = gridDim.x, cta = blockIdx.x;
    const int ts = G / PT;
    const int team = cta / ts, rank = cta % ts;
    const bool streaming = team < PT;
    const uint32_t bar_full  = smem_base + SM_BARS;
    const uint32_t bar_empty = bar_full + NSLOTS * 8;

    if (tid == 0) {
        for (int i = 0; i < NSLOTS; i++) { mbar_init(bar_full + i * 8, 1); mbar_init(bar_empty + i * 8, 1); }
        asm volatile("fence.mbarrier_init.release.cluster;" ::: "memory");
        asm volatile("fence.proxy.async.shared::cta;" ::: "memory");
    }
    __syncthreads();

    if (warp == NCW) {
        if (lane == 0) {
            uint64_t pol;
            asm volatile("createpolicy.fractional.L2::evict_first.b64 %0, 1.0;" : "=l"(pol));
            int slot = 0; uint32_t ph = 0;
            if (streaming) {
                for (int u = 0; u < SPT; u++) {
                    const int s = team * SPT + u;
                    const __nv_bfloat16* kb = (s < 8) ? Ak + (size_t)s * SK * DH : Bk + (size_t)(s - 8) * SK * DH;
                    const __nv_bfloat16* vb = (s < 8) ? Av + (size_t)s * SK * DH : Bv + (size_t)(s - 8) * SK * DH;
                    const int j0 = stream_j0(u, rank, ts);
                    const int n = stream_nblk(j0, ts);
                    for (int k = 0; k < n; k++) {
                        const size_t off = (size_t)(j0 + k * ts) * (BLK_ROWS * DH);
                        mbar_wait(bar_empty + slot * 8, ph ^ 1, 3, u * 1000 + k);
                        mbar_expect_tx(bar_full + slot * 8, BLK_BYTES);
                        bulk_g2s(smem_base + SM_RING + slot * BLK_BYTES, kb + off, BLK_BYTES, bar_full + slot * 8, pol);
                        if (++slot == NSLOTS) { slot = 0; ph ^= 1; }
                        mbar_wait(bar_empty + slot * 8, ph ^ 1, 4, u * 1000 + k);
                        mbar_expect_tx(bar_full + slot * 8, BLK_BYTES);
                        bulk_g2s(smem_base + SM_RING + slot * BLK_BYTES, vb + off, BLK_BYTES, bar_full + slot * 8, pol);
                        if (++slot == NSLOTS) { slot = 0; ph ^= 1; }
                    }
                }
            }
            if (cta < NGEMV) {
                const int p = cta >> 6, idx = cta & 63;
                const unsigned char* wsrc = reinterpret_cast<const unsigned char*>((p ? Bwo : Awo) + (size_t)idx * 64 * D_MODEL);
                const int total = 64 * D_MODEL * 2;
                for (int c = 0; c < total; c += BLK_BYTES) {
                    const int bytes = (total - c) < BLK_BYTES ? (total - c) : BLK_BYTES;
                    mbar_wait(bar_empty + slot * 8, ph ^ 1);
                    mbar_expect_tx(bar_full + slot * 8, bytes);
                    bulk_g2s(smem_base + SM_RING + slot * BLK_BYTES, wsrc + c, bytes, bar_full + slot * 8, pol);
                    if (++slot == NSLOTS) { slot = 0; ph ^= 1; }
                }
            }
        }
        return;
    }

    float* red = reinterpret_cast<float*>(smem + SM_RED);
    if (cta < NGEMV) {
        const int p = cta >> 6, idx = cta & 63;
        const __nv_bfloat16* wq = p ? Bwq : Awq;
        const __nv_bfloat16* x  = p ? Bx : Ax;
        const int lane8 = tid & 7, rowg = tid >> 3;
        uint4 w[14];
#pragma unroll
        for (int k = 0; k < 14; k++)
            w[k] = __ldg(reinterpret_cast<const uint4*>(wq + (size_t)(rowg + 32 * k) * 4096 + idx * 64 + lane8 * 8));
        float acc[8];
#pragma unroll
        for (int j = 0; j < 8; j++) acc[j] = 0.f;
#pragma unroll
        for (int k = 0; k < 14; k++) {
            float xv = __bfloat162float(x[rowg + 32 * k]);
            float wf[8];
            unpack8(w[k], wf);
#pragma unroll
            for (int j = 0; j < 8; j++) acc[j] = fmaf(xv, wf[j], acc[j]);
        }
#pragma unroll
        for (int j = 0; j < 8; j++) {
            acc[j] += __shfl_xor_sync(0xffffffffu, acc[j], 8);
            acc[j] += __shfl_xor_sync(0xffffffffu, acc[j], 16);
        }
        if (lane < 8) {
#pragma unroll
            for (int j = 0; j < 8; j++) red[warp * 64 + lane * 8 + j] = acc[j];
        }
        bar_consumers();
        if (tid < 64) {
            float s = 0.f;
#pragma unroll
            for (int w2 = 0; w2 < NCW; w2++) s += red[w2 * 64 + tid];
            g_q[p][idx * 64 + tid] = bf16_round(s);
        }
    }
    bar_consumers();
    if (tid == 0) {
        if (cta < NGEMV) { __threadfence(); atomicAdd(&g_bar_q, 1u); }
        spin_until(&g_bar_q, (unsigned)NGEMV);
    }
    bar_consumers();
    {
        __nv_bfloat16* qs = reinterpret_cast<__nv_bfloat16*>(smem + SM_Q);
        const float* gq = &g_q[0][0];
        for (int i = tid * 4; i < 2 * NHEADS * DH; i += NCT * 4) {
            float4 v = __ldcg(reinterpret_cast<const float4*>(gq + i));
            qs[i] = __float2bfloat16_rn(v.x); qs[i + 1] = __float2bfloat16_rn(v.y);
            qs[i + 2] = __float2bfloat16_rn(v.z); qs[i + 3] = __float2bfloat16_rn(v.w);
        }
    }
    bar_consumers();

    int seq0 = 0;
    if (streaming) {
        for (int u = 0; u < SPT; u++) {
            const int s = team * SPT + u;
            const int j0 = stream_j0(u, rank, ts);
            const int n = stream_nblk(j0, ts);
            if (s < 8) consume_stream<2>(smem, smem_base, warp, lane, seq0, n, 2 * s, s, rank);
            else       consume_stream<1>(smem, smem_base, warp, lane, seq0, n, 16 + (s - 8), s, rank);
            seq0 += n;
        }
    }

    if (tid == 0) {
        __threadfence();
        atomicAdd(&g_bar_part, 1u);
        if (cta < NGEMV) spin_until(&g_bar_part, (unsigned)G);
    }
    bar_consumers();

    if (cta < NGEMV) {
        const int p = cta >> 6, idx = cta & 63;
        const int hq = idx >> 2, q4 = idx & 3;
        const int stream = p ? 8 + hq : (hq >> 1);
        const int hin = p ? 0 : (hq & 1);
        const float* base = &g_part[stream][0][hin][0];
        constexpr int RSTR = 2 * PART_STRIDE;
        float M = -INFINITY;
        for (int c = lane; c < ts; c += 32) M = fmaxf(M, __ldcg(base + c * RSTR + 256));
        M = warp_max(M);
        float L = 0.f;
        for (int c = lane; c < ts; c += 32) L = fmaf(__ldcg(base + c * RSTR + 257), exp2f(__ldcg(base + c * RSTR + 256) - M), L);
        L = warp_sum(L);
        const int d = tid & 63, g = tid >> 6;
        float acc = 0.f;
        for (int c = g; c < ts; c += 4) {
            float w = exp2f(__ldcg(base + c * RSTR + 256) - M);
            acc = fmaf(__ldcg(base + c * RSTR + q4 * 64 + d), w, acc);
        }
        red[g * 64 + d] = acc;
        bar_consumers();
        float* os = reinterpret_cast<float*>(smem + SM_OS);
        if (tid < 64) {
            float s = red[tid] + red[64 + tid] + red[128 + tid] + red[192 + tid];
            os[tid] = bf16_round(s / L);
        }
        {
            int pos = 2 * seq0;
#pragma unroll
            for (int c = 0; c < 4; c++) {
                const int slot = (pos + c) % NSLOTS;
                const uint32_t ph = ((pos + c) / NSLOTS) & 1;
                mbar_wait(bar_full + slot * 8, ph);
            }
        }
        bar_consumers();
        float acc8[8];
#pragma unroll
        for (int j = 0; j < 8; j++) acc8[j] = 0.f;
        const int chunk = tid % 56, rg = tid / 56;
        if (rg < 4) {
            const int pos = 2 * seq0;
#pragma unroll 4
            for (int r = rg * 16; r < rg * 16 + 16; r++) {
                const int byte = r * (D_MODEL * 2) + chunk * 16;
                const int slot = (pos + (byte >> 14)) % NSLOTS;
                uint4 wv = lds128(smem_base + SM_RING + slot * BLK_BYTES + (byte & (BLK_BYTES - 1)));
                float wf[8];
                unpack8(wv, wf);
                const float ov = os[r];
#pragma unroll
                for (int j = 0; j < 8; j++) acc8[j] = fmaf(ov, wf[j], acc8[j]);
            }
        }
        bar_consumers();
        if (rg < 4) {
#pragma unroll
            for (int j = 0; j < 8; j++) red[rg * 448 + chunk * 8 + j] = acc8[j];
        }
        bar_consumers();
        for (int c = tid; c < D_MODEL; c += NCT) {
            g_outp[p][idx][c] = red[c] + red[448 + c] + red[896 + c] + red[1344 + c];
        }
        bar_consumers();
        __shared__ unsigned s_last;
        if (tid == 0) {
            __threadfence();
            unsigned prev = atomicAdd(&g_bar_out[p], 1u);
            s_last = (prev == 63u);
        }
        bar_consumers();
        if (s_last) {
            __threadfence();
            for (int c = tid; c < D_MODEL; c += NCT) {
                float s = 0.f;
#pragma unroll 8
                for (int i = 0; i < 64; i++) s += __ldcg(&g_outp[p][i][c]);
                out[p * D_MODEL + c] = __float2bfloat16_rn(s);
            }
            if (tid == 0) {
                g_bar_out[p] = 0u;
                unsigned prev = atomicAdd(&g_bar_q, 1u << 16);
                if ((prev >> 16) == 1u) { g_bar_part = 0u; __threadfence(); atomicExch(&g_bar_q, 0u); }
            }
        }
    }
}

}

extern "C" void kernel_launch(void* const* d_in, const int* in_sizes, int n_in,
                              void* d_out, int out_size) {
    (void)in_sizes; (void)n_in; (void)out_size;
    static int sm_count = 0;
    if (sm_count == 0) {
        int dev = 0;
        cudaGetDevice(&dev);
        cudaDeviceGetAttribute(&sm_count, cudaDevAttrMultiProcessorCount, dev);
        cudaFuncSetAttribute(fused_decode_kernel, cudaFuncAttributeMaxDynamicSharedMemorySize, SM_TOTAL);
    }
    int grid = sm_count < MAX_G ? sm_count : MAX_G;
    fused_decode_kernel<<<grid, NTHREADS, SM_TOTAL>>>(
        (const __nv_bfloat16*)d_in[0], (const __nv_bfloat16*)d_in[1], (const __nv_bfloat16*)d_in[2],
        (const __nv_bfloat16*)d_in[3], (const __nv_bfloat16*)d_in[4], (const __nv_bfloat16*)d_in[5],
        (const __nv_bfloat16*)d_in[6], (const __nv_bfloat16*)d_in[7], (const __nv_bfloat16*)d_in[8],
        (const __nv_bfloat16*)d_in[9], (__nv_bfloat16*)d_out);
}
```

```cpp
#include <cuda_runtime.h>
#include <cuda_bf16.h>
#include <stdint.h>

namespace {

constexpr int D_MODEL   = 448;
constexpr int DH        = 256;
constexpr int SK        = 32768;
constexpr int NHEADS    = 16;
constexpr int NSTREAM   = 24;
constexpr int BLK_ROWS  = 32;
constexpr int BLK_BYTES = BLK_ROWS * DH * 2;
constexpr int NBLK      = SK / BLK_ROWS;
constexpr int NSLOTS    = 12;
#define INFLIGHT 4
constexpr int NCW       = 8;
constexpr int NCT       = NCW * 32;
constexpr int NTHREADS  = NCT + 32;
#define P_TEAMS 2
constexpr int PT        = P_TEAMS;
constexpr int SPT       = NSTREAM / PT;
constexpr int MAX_G     = 132;
constexpr int MAX_TS    = MAX_G / PT;
constexpr int NGEMV     = 128;

constexpr int SM_RING   = 0;
constexpr int SM_ST_O   = SM_RING + NSLOTS * BLK_BYTES;
constexpr int SM_ST_ML  = SM_ST_O + NCW * 2 * 256 * 4;
constexpr int SM_Q      = SM_ST_ML + NCW * 2 * 2 * 4;
constexpr int SM_RED    = SM_ST_O;
constexpr int SM_OS     = SM_Q + 32 * 256 * 2;
constexpr int SM_BARS   = SM_OS + 64 * 4;
constexpr int SM_META   = SM_BARS + 2 * NSLOTS * 8;
constexpr int SM_TOTAL  = SM_META + NSLOTS * 4;
constexpr int META_END  = 0x7fffffff;

constexpr float SCALE_LOG2E = 0.0625f * 1.4426950408889634f;

__device__ unsigned g_q[2][NHEADS * DH];
__device__ unsigned g_epoch;
__device__ float    g_part[NSTREAM][MAX_TS][2][DH];
__device__ float2   g_stat[NSTREAM][2][MAX_TS + 4];
__device__ float    g_outp[2][64][D_MODEL];
__device__ unsigned g_fin;
__device__ unsigned g_ticket[PT];
__device__ unsigned g_bar_part;
__device__ unsigned g_bar_out[2];

__device__ __forceinline__ uint32_t smem_u32(const void* p) { return (uint32_t)__cvta_generic_to_shared(p); }
__device__ __forceinline__ void mbar_init(uint32_t bar, uint32_t count) {
    asm volatile("mbarrier.init.shared::cta.b64 [%0], %1;" :: "r"(bar), "r"(count) : "memory");
}
__device__ __forceinline__ void mbar_expect_tx(uint32_t bar, uint32_t bytes) {
    asm volatile("mbarrier.arrive.expect_tx.shared::cta.b64 _, [%0], %1;" :: "r"(bar), "r"(bytes) : "memory");
}
__device__ __forceinline__ void mbar_arrive(uint32_t bar) {
    asm volatile("mbarrier.arrive.shared::cta.b64 _, [%0];" :: "r"(bar) : "memory");
}
#define HANG(site, info) __trap()
__device__ __forceinline__ void mbar_wait(uint32_t bar, uint32_t parity, unsigned site = 0, unsigned info = 0) {
    uint32_t done;
    uint32_t spins = 0;
    do {
        asm volatile("{ .reg .pred p; mbarrier.try_wait.parity.shared::cta.b64 p, [%1], %2; selp.u32 %0, 1, 0, p; }"
                     : "=r"(done) : "r"(bar), "r"(parity) : "memory");
        if (++spins > (1u << 22)) { HANG(site, info); break; }
    } while (!done);
}
__device__ __forceinline__ void bulk_g2s(uint32_t dst, const void* src, uint32_t bytes, uint32_t bar, uint64_t pol) {
    asm volatile("cp.async.bulk.shared::cluster.global.mbarrier::complete_tx::bytes.L2::cache_hint [%0], [%1], %2, [%3], %4;"
                 :: "r"(dst), "l"(src), "r"(bytes), "r"(bar), "l"(pol) : "memory");
}
__device__ __forceinline__ uint4 lds128(uint32_t addr) {
    uint4 v;
    asm volatile("ld.shared.v4.u32 {%0,%1,%2,%3}, [%4];" : "=r"(v.x), "=r"(v.y), "=r"(v.z), "=r"(v.w) : "r"(addr));
    return v;
}
__device__ __forceinline__ void bar_consumers() { asm volatile("bar.sync 1, %0;" :: "n"(NCT) : "memory"); }
__device__ __forceinline__ unsigned ld_acquire(const unsigned* p) {
    unsigned v;
    asm volatile("ld.acquire.gpu.global.u32 %0, [%1];" : "=r"(v) : "l"(p) : "memory");
    return v;
}
__device__ __forceinline__ void spin_until(const unsigned* p, unsigned target) {
    unsigned spins = 0;
    while (ld_acquire(p) < target) {
        if (++spins > (1u << 22)) { HANG(99, target); break; }
    }
}
#define TS(i)
#define TSP(i)
__device__ __forceinline__ float bf_lo(uint32_t u) { return __uint_as_float(u << 16); }
__device__ __forceinline__ float bf_hi(uint32_t u) { return __uint_as_float(u & 0xffff0000u); }
__device__ __forceinline__ void unpack8(const uint4& v, float (&f)[8]) {
    f[0] = bf_lo(v.x); f[1] = bf_hi(v.x); f[2] = bf_lo(v.y); f[3] = bf_hi(v.y);
    f[4] = bf_lo(v.z); f[5] = bf_hi(v.z); f[6] = bf_lo(v.w); f[7] = bf_hi(v.w);
}
__device__ __forceinline__ float bf16_round(float x) { return __bfloat162float(__float2bfloat16_rn(x)); }

__device__ __forceinline__ float transpose_reduce32(float (&v)[32], int lane) {
#pragma unroll
    for (int i = 0; i < 16; i++) {
        bool hi = lane & 16;
        float send = hi ? v[i] : v[i + 16];
        float keep = hi ? v[i + 16] : v[i];
        v[i] = keep + __shfl_xor_sync(0xffffffffu, send, 16);
    }
#pragma unroll
    for (int i = 0; i < 8; i++) {
        bool hi = lane & 8;
        float send = hi ? v[i] : v[i + 8];
        float keep = hi ? v[i + 8] : v[i];
        v[i] = keep + __shfl_xor_sync(0xffffffffu, send, 8);
    }
#pragma unroll
    for (int i = 0; i < 4; i++) {
        bool hi = lane & 4;
        float send = hi ? v[i] : v[i + 4];
        float keep = hi ? v[i + 4] : v[i];
        v[i] = keep + __shfl_xor_sync(0xffffffffu, send, 4);
    }
#pragma unroll
    for (int i = 0; i < 2; i++) {
        bool hi = lane & 2;
        float send = hi ? v[i] : v[i + 2];
        float keep = hi ? v[i + 2] : v[i];
        v[i] = keep + __shfl_xor_sync(0xffffffffu, send, 2);
    }
    {
        bool hi = lane & 1;
        float send = hi ? v[0] : v[1];
        float keep = hi ? v[1] : v[0];
        v[0] = keep + __shfl_xor_sync(0xffffffffu, send, 1);
    }
    return v[0];
}
__device__ __forceinline__ float warp_max(float v) {
#pragma unroll
    for (int o = 16; o > 0; o >>= 1) v = fmaxf(v, __shfl_xor_sync(0xffffffffu, v, o));
    return v;
}
__device__ __forceinline__ float warp_sum(float v) {
#pragma unroll
    for (int o = 16; o > 0; o >>= 1) v += __shfl_xor_sync(0xffffffffu, v, o);
    return v;
}

__device__ __forceinline__ int stream_j0(int u, int rank, int ts) {
    int off = (u * (NBLK % ts)) % ts;
    int j0 = rank + off;
    return j0 >= ts ? j0 - ts : j0;
}
__device__ __forceinline__ int stream_nblk(int j0, int ts) { return (NBLK - j0 + ts - 1) / ts; }

struct WarpState {
    float q[2][8];
    float o[2][8];
    float m_run[2], l_lane[2];
};

__device__ __forceinline__ void state_reset(WarpState& st, uint32_t smem_base, int lane, int s) {
    const int qhead0 = (s < 8) ? 2 * s : 16 + (s - 8);
#pragma unroll
    for (int h = 0; h < 2; h++) {
        const int qh = (qhead0 + h) < 32 ? (qhead0 + h) : 31;
        uint4 qq = lds128(smem_base + SM_Q + qh * (DH * 2) + lane * 16);
        unpack8(qq, st.q[h]);
        st.m_run[h] = -INFINITY; st.l_lane[h] = 0.f;
#pragma unroll
        for (int j = 0; j < 8; j++) st.o[h][j] = 0.f;
    }
}

template <int NH>
__device__ __forceinline__ void process_block(WarpState& st, uint32_t smem_base, int lane, int slot, int slotv, uint32_t phv, int posv) {
    const uint32_t bar_full  = smem_base + SM_BARS;
    const uint32_t bar_empty = bar_full + NSLOTS * 8;
    const uint32_t kb = smem_base + SM_RING + slot * BLK_BYTES + lane * 16;
    float acc[NH][32];
#pragma unroll
    for (int r = 0; r < 32; r++) {
        uint4 kk = lds128(kb + r * (DH * 2));
        float kf[8];
        unpack8(kk, kf);
#pragma unroll
        for (int h = 0; h < NH; h++) {
            float a = st.q[h][0] * kf[0];
#pragma unroll
            for (int j = 1; j < 8; j++) a = fmaf(st.q[h][j], kf[j], a);
            acc[h][r] = a;
        }
    }
    __syncwarp();
    if (lane == 0) mbar_arrive(bar_empty + slot * 8);

    float p[NH];
#pragma unroll
    for (int h = 0; h < NH; h++) {
        float s = transpose_reduce32(acc[h], lane);
        float t = bf16_round(s) * SCALE_LOG2E;
        float bm = warp_max(t);
        float m_new = fmaxf(st.m_run[h], bm);
        float corr = exp2f(st.m_run[h] - m_new);
        p[h] = exp2f(t - m_new);
        st.l_lane[h] = st.l_lane[h] * corr + p[h];
        st.m_run[h] = m_new;
#pragma unroll
        for (int j = 0; j < 8; j++) st.o[h][j] *= corr;
    }
    mbar_wait(bar_full + slotv * 8, phv, 2, posv);
    const uint32_t vb = smem_base + SM_RING + slotv * BLK_BYTES + lane * 16;
#pragma unroll
    for (int r = 0; r < 32; r++) {
        uint4 vv = lds128(vb + r * (DH * 2));
        float vf[8];
        unpack8(vv, vf);
#pragma unroll
        for (int h = 0; h < NH; h++) {
            float pr = __shfl_sync(0xffffffffu, p[h], r);
#pragma unroll
            for (int j = 0; j < 8; j++) st.o[h][j] = fmaf(pr, vf[j], st.o[h][j]);
        }
    }
    __syncwarp();
    if (lane == 0) mbar_arrive(bar_empty + slotv * 8);
}

__device__ __forceinline__ void flush_stream(WarpState& st, unsigned char* smem, int warp, int lane, int s, int rank) {
    const int nh = (s < 8) ? 2 : 1;
    float* st_o  = reinterpret_cast<float*>(smem + SM_ST_O);
    float* st_ml = reinterpret_cast<float*>(smem + SM_ST_ML);
#pragma unroll
    for (int h = 0; h < 2; h++) {
        if (h < nh) {
            float lw = warp_sum(st.l_lane[h]);
            float4* dst = reinterpret_cast<float4*>(st_o + (warp * 2 + h) * DH + lane * 8);
            dst[0] = make_float4(st.o[h][0], st.o[h][1], st.o[h][2], st.o[h][3]);
            dst[1] = make_float4(st.o[h][4], st.o[h][5], st.o[h][6], st.o[h][7]);
            if (lane == 0) { st_ml[(warp * 2 + h) * 2] = st.m_run[h]; st_ml[(warp * 2 + h) * 2 + 1] = lw; }
        }
    }
    bar_consumers();
    const int t = warp * 32 + lane;
#pragma unroll
    for (int h = 0; h < 2; h++) {
        if (h < nh) {
            float M = -INFINITY;
#pragma unroll
            for (int w = 0; w < NCW; w++) M = fmaxf(M, st_ml[(w * 2 + h) * 2]);
            float acc = 0.f, L = 0.f;
            if (M != -INFINITY) {
#pragma unroll
                for (int w = 0; w < NCW; w++) {
                    float sc = exp2f(st_ml[(w * 2 + h) * 2] - M);
                    acc = fmaf(st_o[(w * 2 + h) * DH + t], sc, acc);
                    L = fmaf(st_ml[(w * 2 + h) * 2 + 1], sc, L);
                }
            }
            g_part[s][rank][h][t] = acc;
            if (t == 0) g_stat[s][h][rank] = make_float2(M, L);
        }
    }
    bar_consumers();
}

__global__ void __launch_bounds__(NTHREADS, 1)
fused_decode_kernel(const __nv_bfloat16* __restrict__ Ax, const __nv_bfloat16* __restrict__ Ak,
                    const __nv_bfloat16* __restrict__ Av, const __nv_bfloat16* __restrict__ Awq,
                    const __nv_bfloat16* __restrict__ Awo, const __nv_bfloat16* __restrict__ Bx,
                    const __nv_bfloat16* __restrict__ Bk, const __nv_bfloat16* __restrict__ Bv,
                    const __nv_bfloat16* __restrict__ Bwq, const __nv_bfloat16* __restrict__ Bwo,
                    __nv_bfloat16* __restrict__ out) {
    extern __shared__ __align__(128) unsigned char smem[];
    const uint32_t smem_base = smem_u32(smem);
    const int tid = threadIdx.x, warp = tid >> 5, lane = tid & 31;
    const int G = gridDim.x, cta = blockIdx.x;
    const int ts = G / PT;
    const int team = cta / ts, rank = cta % ts;
    const bool streaming = team < PT;
    const uint32_t bar_full  = smem_base + SM_BARS;
    const uint32_t bar_empty = bar_full + NSLOTS * 8;

    TS(0);
    uint4 wreg[14];
    float xreg[14];
    const unsigned epoch = *(volatile unsigned*)&g_epoch;
    const unsigned tag = (epoch & 0x7fffu) | 0x8000u;
    if (warp < NCW && cta < NGEMV) {
        const int p = cta >> 6, idx = cta & 63;
        const __nv_bfloat16* wq = p ? Bwq : Awq;
        const __nv_bfloat16* x  = p ? Bx : Ax;
        const int lane8 = tid & 7, rowg = tid >> 3;
#pragma unroll
        for (int k = 0; k < 14; k++) {
            const __nv_bfloat16* src = wq + (size_t)(rowg + 32 * k) * 4096 + idx * 64 + lane8 * 8;
            asm volatile("ld.global.nc.L1::no_allocate.v4.u32 {%0,%1,%2,%3}, [%4];"
                         : "=r"(wreg[k].x), "=r"(wreg[k].y), "=r"(wreg[k].z), "=r"(wreg[k].w) : "l"(src));
        }
#pragma unroll
        for (int k = 0; k < 14; k++) xreg[k] = __bfloat162float(x[rowg + 32 * k]);
    }
    if (tid == NCT) {
        for (int i = 0; i < NSLOTS; i++) { mbar_init(bar_full + i * 8, 1); mbar_init(bar_empty + i * 8, (i & 1) ? 1 : NCW); }
        asm volatile("fence.mbarrier_init.release.cluster;" ::: "memory");
        asm volatile("fence.proxy.async.shared::cta;" ::: "memory");
    }
    __syncthreads();

    if (warp == NCW) {
        if (lane == 0) {
            uint64_t pol;
            asm volatile("createpolicy.fractional.L2::evict_first.b64 %0, 1.0;" : "=l"(pol));
            int slot = 0; uint32_t ph = 0;
            int lslot = 0; uint32_t lph = 0; int issued = 0;
            volatile int* meta = reinterpret_cast<volatile int*>(smem + SM_META);
            if (streaming) {
                constexpr unsigned TOTAL = SPT * NBLK;
                unsigned tA = atomicAdd(&g_ticket[team], 1u);
                unsigned tB = atomicAdd(&g_ticket[team], 1u);
                for (;;) {
                    const unsigned t = tA;
                    tA = tB;
                    if (t >= TOTAL) break;
                    tB = atomicAdd(&g_ticket[team], 1u);
                    const int u = (int)(t >> 10), j = (int)(t & (NBLK - 1));
                    const int s = team * SPT + u;
                    const __nv_bfloat16* kb = (s < 8) ? Ak + (size_t)s * SK * DH : Bk + (size_t)(s - 8) * SK * DH;
                    const __nv_bfloat16* vb = (s < 8) ? Av + (size_t)s * SK * DH : Bv + (size_t)(s - 8) * SK * DH;
                    const size_t off = (size_t)j * (BLK_ROWS * DH);
#pragma unroll
                    for (int kv = 0; kv < 2; kv++) {
                        if (issued >= INFLIGHT) {
                            mbar_wait(bar_full + lslot * 8, lph, 7, issued);
                            if (++lslot == NSLOTS) { lslot = 0; lph ^= 1; }
                        }
                        mbar_wait(bar_empty + slot * 8, ph ^ 1, 3, t);
                        if (kv == 0) meta[slot] = u;
                        mbar_expect_tx(bar_full + slot * 8, BLK_BYTES);
                        bulk_g2s(smem_base + SM_RING + slot * BLK_BYTES, (kv ? vb : kb) + off, BLK_BYTES, bar_full + slot * 8, pol);
                        issued++;
                        if (++slot == NSLOTS) { slot = 0; ph ^= 1; }
                    }
                }
            }
            mbar_wait(bar_empty + slot * 8, ph ^ 1, 3, 0);
            meta[slot] = META_END;
            mbar_arrive(bar_full + slot * 8);
            if (++slot == NSLOTS) { slot = 0; ph ^= 1; }
            TSP(6);
            if (cta < NGEMV) {
                const int p = cta >> 6, idx = cta & 63;
                const unsigned char* wsrc = reinterpret_cast<const unsigned char*>((p ? Bwo : Awo) + (size_t)idx * 64 * D_MODEL);
                const int total = 64 * D_MODEL * 2;
                for (int c = 0; c < total; c += BLK_BYTES) {
                    const int bytes = (total - c) < BLK_BYTES ? (total - c) : BLK_BYTES;
                    mbar_wait(bar_empty + slot * 8, ph ^ 1);
                    mbar_expect_tx(bar_full + slot * 8, bytes);
                    bulk_g2s(smem_base + SM_RING + slot * BLK_BYTES, wsrc + c, bytes, bar_full + slot * 8, pol);
                    if (++slot == NSLOTS) { slot = 0; ph ^= 1; }
                }
            }
        }
        return;
    }

    float* red = reinterpret_cast<float*>(smem + SM_RED);
    if (cta < NGEMV) {
        const int p = cta >> 6, idx = cta & 63;
        float acc[8];
#pragma unroll
        for (int j = 0; j < 8; j++) acc[j] = 0.f;
#pragma unroll
        for (int k = 0; k < 14; k++) {
            float wf[8];
            unpack8(wreg[k], wf);
#pragma unroll
            for (int j = 0; j < 8; j++) acc[j] = fmaf(xreg[k], wf[j], acc[j]);
        }
#pragma unroll
        for (int j = 0; j < 8; j++) {
            acc[j] += __shfl_xor_sync(0xffffffffu, acc[j], 8);
            acc[j] += __shfl_xor_sync(0xffffffffu, acc[j], 16);
        }
        if (lane < 8) {
#pragma unroll
            for (int j = 0; j < 8; j++) red[warp * 64 + lane * 8 + j] = acc[j];
        }
        bar_consumers();
        TS(7);
        if (tid < 64) {
            float s = 0.f;
#pragma unroll
            for (int w2 = 0; w2 < NCW; w2++) s += red[w2 * 64 + tid];
            const unsigned bits = (unsigned)__bfloat16_as_ushort(__float2bfloat16_rn(s));
            asm volatile("st.global.relaxed.gpu.u32 [%0], %1;" :: "l"(&g_q[p][idx * 64 + tid]), "r"((bits << 16) | tag) : "memory");
        }
    }
    {
        uint2* qs = reinterpret_cast<uint2*>(smem + SM_Q);
        const uint4* gq = reinterpret_cast<const uint4*>(&g_q[0][0]);
        uint4 v[8];
        unsigned spins = 0;
        bool ok;
        do {
            ok = true;
#pragma unroll
            for (int i = 0; i < 8; i++) {
                asm volatile("ld.global.relaxed.gpu.v4.u32 {%0,%1,%2,%3}, [%4];"
                             : "=r"(v[i].x), "=r"(v[i].y), "=r"(v[i].z), "=r"(v[i].w) : "l"(gq + tid + i * NCT) : "memory");
            }
#pragma unroll
            for (int i = 0; i < 8; i++)
                ok = ok && ((v[i].x & 0xffffu) == tag) && ((v[i].y & 0xffffu) == tag) && ((v[i].z & 0xffffu) == tag) && ((v[i].w & 0xffffu) == tag);
            if (++spins > (1u << 22)) { HANG(98, 0); break; }
        } while (!ok);
#pragma unroll
        for (int i = 0; i < 8; i++)
            qs[tid + i * NCT] = make_uint2((v[i].x >> 16) | (v[i].y & 0xffff0000u), (v[i].z >> 16) | (v[i].w & 0xffff0000u));
    }
    bar_consumers();
    TS(1);

    int seq = 0;
    {
        WarpState st;
        int cur_u = 0;
        state_reset(st, smem_base, lane, team * SPT);
        const volatile int* meta = reinterpret_cast<const volatile int*>(smem + SM_META);
        for (;; seq++) {
            const int pos = 2 * seq;
            const int slot = pos % NSLOTS;
            const uint32_t ph = (pos / NSLOTS) & 1;
            mbar_wait(bar_full + slot * 8, ph, 1, pos);
            const int u = meta[slot];
            const bool mine = (seq & (NCW - 1)) == warp;
            if (!mine || u == META_END) { __syncwarp(); if (lane == 0) mbar_arrive(bar_empty + slot * 8); }
            if (u != cur_u) {
                const int uend = u < SPT ? u : SPT;
                while (cur_u < uend) {
                    flush_stream(st, smem, warp, lane, team * SPT + cur_u, rank);
                    cur_u++;
                    if (cur_u < SPT) state_reset(st, smem_base, lane, team * SPT + cur_u);
                }
                if (u == META_END) break;
            }
            const int posv = pos + 1;
            const int slotv = posv % NSLOTS;
            const uint32_t phv = (posv / NSLOTS) & 1;
            if (mine) {
                if (team * SPT + u < 8) process_block<2>(st, smem_base, lane, slot, slotv, phv, posv);
                else                    process_block<1>(st, smem_base, lane, slot, slotv, phv, posv);
            } else {
                mbar_wait(bar_full + slotv * 8, phv, 6, posv);
            }
        }
    }
    const int pos_wo = 2 * seq + 1;
    TS(2);
    if (tid == 0) {
        __threadfence();
        atomicAdd(&g_bar_part, 1u);
        if (cta < NGEMV) spin_until(&g_bar_part, (unsigned)G);
    }
    bar_consumers();
    TS(3);

    if (cta < NGEMV) {
        const int p = cta >> 6, idx = cta & 63;
        const int hq = idx >> 2, q4 = idx & 3;
        const int stream = p ? 8 + hq : (hq >> 1);
        const int hin = p ? 0 : (hq & 1);
        const int cg = tid >> 4, d4 = tid & 15;
        float4 pv[(MAX_TS + 15) / 16];
#pragma unroll
        for (int i = 0; i < (MAX_TS + 15) / 16; i++) {
            const int c = cg + 16 * i;
            pv[i] = (c < ts) ? __ldcg(reinterpret_cast<const float4*>(&g_part[stream][c][hin][q4 * 64 + d4 * 4])) : make_float4(0.f, 0.f, 0.f, 0.f);
        }
        float2 st[(MAX_TS + 31) / 32];
#pragma unroll
        for (int i = 0; i < (MAX_TS + 31) / 32; i++) {
            const int c = lane + 32 * i;
            st[i] = (c < ts) ? __ldcg(&g_stat[stream][hin][c]) : make_float2(-INFINITY, 0.f);
        }
        float M = -INFINITY;
#pragma unroll
        for (int i = 0; i < (MAX_TS + 31) / 32; i++) M = fmaxf(M, st[i].x);
        M = warp_max(M);
        float wgt[(MAX_TS + 31) / 32];
        float L = 0.f;
#pragma unroll
        for (int i = 0; i < (MAX_TS + 31) / 32; i++) { wgt[i] = exp2f(st[i].x - M); L = fmaf(st[i].y, wgt[i], L); }
        L = warp_sum(L);
        float4 a4 = make_float4(0.f, 0.f, 0.f, 0.f);
#pragma unroll
        for (int i = 0; i < (MAX_TS + 15) / 16; i++) {
            const int c = cg + 16 * i;
            float w = 0.f;
#pragma unroll
            for (int r2 = 0; r2 < (MAX_TS + 31) / 32; r2++) {
                float wv = __shfl_sync(0xffffffffu, wgt[r2], c & 31);
                if ((c >> 5) == r2) w = wv;
            }
            a4.x = fmaf(pv[i].x, w, a4.x); a4.y = fmaf(pv[i].y, w, a4.y);
            a4.z = fmaf(pv[i].z, w, a4.z); a4.w = fmaf(pv[i].w, w, a4.w);
        }
        *reinterpret_cast<float4*>(&red[cg * 64 + d4 * 4]) = a4;
        bar_consumers();
        float* os = reinterpret_cast<float*>(smem + SM_OS);
        if (tid < 64) {
            float s2 = 0.f;
#pragma unroll
            for (int g = 0; g < 16; g++) s2 += red[g * 64 + tid];
            os[tid] = bf16_round(s2 / L);
        }
        {
            int pos = pos_wo;
#pragma unroll
            for (int c = 0; c < 4; c++) {
                const int slot = (pos + c) % NSLOTS;
                const uint32_t ph = ((pos + c) / NSLOTS) & 1;
                mbar_wait(bar_full + slot * 8, ph);
            }
        }
        bar_consumers();
        float acc8[8];
#pragma unroll
        for (int j = 0; j < 8; j++) acc8[j] = 0.f;
        const int chunk = tid % 56, rg = tid / 56;
        if (rg < 4) {
            const int pos = pos_wo;
#pragma unroll 4
            for (int r = rg * 16; r < rg * 16 + 16; r++) {
                const int byte = r * (D_MODEL * 2) + chunk * 16;
                const int slot = (pos + (byte >> 14)) % NSLOTS;
                uint4 wv = lds128(smem_base + SM_RING + slot * BLK_BYTES + (byte & (BLK_BYTES - 1)));
                float wf[8];
                unpack8(wv, wf);
                const float ov = os[r];
#pragma unroll
                for (int j = 0; j < 8; j++) acc8[j] = fmaf(ov, wf[j], acc8[j]);
            }
        }
        bar_consumers();
        if (rg < 4) {
#pragma unroll
            for (int j = 0; j < 8; j++) red[rg * 448 + chunk * 8 + j] = acc8[j];
        }
        bar_consumers();
        for (int c = tid; c < D_MODEL; c += NCT) {
            g_outp[p][idx][c] = red[c] + red[448 + c] + red[896 + c] + red[1344 + c];
        }
        bar_consumers();
        TS(4);
        __shared__ unsigned s_last;
        if (tid == 0) {
            __threadfence();
            unsigned prev = atomicAdd(&g_bar_out[p], 1u);
            s_last = (prev == 63u);
        }
        bar_consumers();
        if (s_last) {
            __threadfence();
            {
                const int c4 = tid % 112, half = tid / 112;
                float4 sacc = make_float4(0.f, 0.f, 0.f, 0.f);
                if (half < 2) {
                    float4 v[32];
#pragma unroll
                    for (int i = 0; i < 32; i++) v[i] = __ldcg(reinterpret_cast<const float4*>(&g_outp[p][half * 32 + i][c4 * 4]));
#pragma unroll
                    for (int i = 0; i < 32; i++) { sacc.x += v[i].x; sacc.y += v[i].y; sacc.z += v[i].z; sacc.w += v[i].w; }
                    *reinterpret_cast<float4*>(&red[half * 448 + c4 * 4]) = sacc;
                }
                bar_consumers();
                for (int c = tid; c < D_MODEL; c += NCT) out[p * D_MODEL + c] = __float2bfloat16_rn(red[c] + red[448 + c]);
            }
            TS(5);
            if (tid == 0) {
                g_bar_out[p] = 0u;
                unsigned prev = atomicAdd(&g_fin, 1u);
                if (prev == 1u) { g_bar_part = 0u; g_fin = 0u; for (int i = 0; i < PT; i++) g_ticket[i] = 0u; g_epoch = epoch + 1u; }
            }
        }
    }
}

}

extern "C" void kernel_launch(void* const* d_in, const int* in_sizes, int n_in,
                              void* d_out, int out_size) {
    (void)in_sizes; (void)n_in; (void)out_size;
    static int sm_count = 0;
    if (sm_count == 0) {
        int dev = 0;
        cudaGetDevice(&dev);
        cudaDeviceGetAttribute(&sm_count, cudaDevAttrMultiProcessorCount, dev);
        cudaFuncSetAttribute(fused_decode_kernel, cudaFuncAttributeMaxDynamicSharedMemorySize, SM_TOTAL);
    }
    int grid = sm_count < MAX_G ? sm_count : MAX_G;
    fused_decode_kernel<<<grid, NTHREADS, SM_TOTAL>>>(
        (const __nv_bfloat16*)d_in[0], (const __nv_bfloat16*)d_in[1], (const __nv_bfloat16*)d_in[2],
        (const __nv_bfloat16*)d_in[3], (const __nv_bfloat16*)d_in[4], (const __nv_bfloat16*)d_in[5],
        (const __nv_bfloat16*)d_in[6], (const __nv_bfloat16*)d_in[7], (const __nv_bfloat16*)d_in[8],
        (const __nv_bfloat16*)d_in[9], (__nv_bfloat16*)d_out);
}
```
